```python
import torch

def _softmax(x, axis=-1):
    return torch.softmax(x, dim=axis)
def _gelu(x):
    return torch.nn.functional.gelu(x, approximate="tanh")
def _silu(x):
    return torch.nn.functional.silu(x)
def _sigmoid(x):
    return torch.sigmoid(x)
def _layernorm(x, axis=-1, eps=1e-5):
    m = x.mean(dim=axis, keepdim=True)
    v = x.var(dim=axis, keepdim=True, unbiased=False)
    return (x - m) / torch.sqrt(v + eps)
def _scatter_add(tgt, idx, src, axis=0):
    return tgt.clone().index_add_(axis, idx, src)
def _segment_sum(src, seg, n):
    out = torch.zeros((n,) + src.shape[1:], dtype=src.dtype)
    return out.index_add_(0, seg, src)
def _pad(x, pw):
    flat = tuple(v for pair in reversed(pw) for v in pair)
    return torch.nn.functional.pad(x, flat)

kernel_name = 'standalone__edge_featured_mpnn_egc__graph'

def setup_inputs():

    _w = (lambda a: (lambda t: t.to(torch.bfloat16) if t.is_floating_point() else t)(torch.as_tensor(a)))
    N, deg, D, De = 50000, 16, 64, max(4, 1)
    E = N * deg
    return {
        "x": _w((lambda *s: torch.randn(*s, dtype=torch.bfloat16) * 0.2)(N, D)),
        "e_attr": _w((lambda *s: torch.randn(*s, dtype=torch.bfloat16) * 0.2)(E, De)),
        "src": _w((lambda lo, hi, *s: torch.randint(lo, hi, s))(0, N, E).to(torch.int64)),
        "dst": _w((lambda lo, hi, *s: torch.randint(lo, hi, s))(0, N, E).to(torch.int64)),
        "u_w": _w((lambda *s: torch.randn(*s, dtype=torch.bfloat16) * 0.05)(D, D)),
        "v_w": _w((lambda *s: torch.randn(*s, dtype=torch.bfloat16) * 0.05)(D, D)),
        "g_w": _w((lambda *s: torch.randn(*s, dtype=torch.bfloat16) * 0.2)(2 * D + De, D)),
    }

def reference(x, e_attr, src, dst, u_w, v_w, g_w):
    N, D = x.shape
    g_in = torch.concatenate([x[dst], x[src], e_attr], axis=-1)
    eta = _sigmoid(g_in @ g_w)
    hv = x @ v_w
    msg = eta * hv[src]
    agg = _segment_sum(msg, dst, N)
    return _silu(x @ u_w + agg)
```

```cpp
#include <cuda_runtime.h>
#include <cuda_bf16.h>
#include <stdint.h>

namespace egc {

constexpr int NN   = 50000;
constexpr int NE   = 800000;
constexpr int NB   = 132;
constexpr int NT   = 512;
constexpr int NPB  = (NN + NB - 1) / NB;
constexpr int CH   = (((NE + NB - 1) / NB) + 15) & ~15;
constexpr int PC   = CH / 4;
constexpr int CAP  = 7168;
constexpr int XA   = CAP * 4;
constexpr int XAB  = CAP * 6;
constexpr int NG   = 96;
constexpr uint32_t MAGIC = (uint32_t)(((1ull << 32) + NPB - 1) / NPB);
static_assert(NE > (NB - 1) * CH + 3 * PC && CH + NB * 7 < CAP && NN <= 65536 && NPB <= NG * 4 - 4 && NPB > NG * 4 - 8 && PC <= 1536 && NE % 16 == 0 && NE < (1 << 20), "shape");

constexpr int SM_AU   = 0;
constexpr int SM_RING = 98304;
constexpr int RINGW   = 24576;
constexpr int SM_REC  = SM_RING + 3 * RINGW;
constexpr int SM_KEY  = SM_REC + XA;
constexpr int SM_MISC = SM_REC + CAP * 8;
constexpr int SM_WE   = SM_RING + XAB;
constexpr int SM_CNT  = SM_REC - NG * 128;
constexpr int M_HIST = 0, M_MASK = 640, M_VAR = 768, M_TOT = 800, M_ZEND = 1184;
constexpr int M_BOFF = 1184, M_SEG = 1824, M_BAR = 2784;
constexpr uint32_t TRASH = (NG - 1) << 4;
constexpr int SM_TOTAL = SM_MISC + 2976;
constexpr int B_IN = 0, B_W = 64, B_X = 80;
constexpr uint32_t PAD_B = 0x800;
constexpr int SPIN_LIMIT = 1 << 22;
static_assert(SM_TOTAL <= 232448 && SM_WE + 16896 <= SM_CNT, "smem");

__device__ __align__(128) char g_rec[NB * XAB];
constexpr int TABP = 160;
__device__ __align__(128) uint32_t g_tab[NB * TABP];

__device__ __forceinline__ uint64_t mk64(uint32_t lo, uint32_t hi) {
    uint64_t r; asm("mov.b64 %0,{%1,%2};" : "=l"(r) : "r"(lo), "r"(hi)); return r;
}
__device__ __forceinline__ uint32_t lds32(uint32_t a) { uint32_t v; asm volatile("ld.shared.u32 %0,[%1];" : "=r"(v) : "r"(a) : "memory"); return v; }
__device__ __forceinline__ uint2 lds64(uint32_t a) { uint2 v; asm volatile("ld.shared.v2.u32 {%0,%1},[%2];" : "=r"(v.x), "=r"(v.y) : "r"(a) : "memory"); return v; }
__device__ __forceinline__ uint4 lds128(uint32_t a) { uint4 v; asm volatile("ld.shared.v4.u32 {%0,%1,%2,%3},[%4];" : "=r"(v.x), "=r"(v.y), "=r"(v.z), "=r"(v.w) : "r"(a) : "memory"); return v; }
__device__ __forceinline__ void sts32(uint32_t a, uint32_t v) { asm volatile("st.shared.u32 [%0],%1;" ::"r"(a), "r"(v) : "memory"); }
__device__ __forceinline__ void sts64(uint32_t a, uint32_t x, uint32_t y) { asm volatile("st.shared.v2.u32 [%0],{%1,%2};" ::"r"(a), "r"(x), "r"(y) : "memory"); }
__device__ __forceinline__ uint32_t atoms_add(uint32_t a, uint32_t v) { uint32_t r; asm volatile("atom.shared.add.u32 %0,[%1],%2;" : "=r"(r) : "r"(a), "r"(v) : "memory"); return r; }
__device__ __forceinline__ void cp16(uint32_t d, const void* s) { asm volatile("cp.async.cg.shared.global [%0],[%1],16;" ::"r"(d), "l"(s) : "memory"); }
__device__ __forceinline__ void cp16row(uint32_t d, uint32_t row, uint64_t base) {
    asm volatile("{.reg .u64 p; mad.wide.u32 p,%1,128,%2; cp.async.cg.shared.global [%0],[p],16;}" ::"r"(d), "r"(row), "l"(base) : "memory");
}
__device__ __forceinline__ void cp_arrive(uint32_t bar) { asm volatile("cp.async.mbarrier.arrive.noinc.shared.b64 [%0];" ::"r"(bar) : "memory"); }
__device__ __forceinline__ void cp_commit() { asm volatile("cp.async.commit_group;" ::: "memory"); }
template <int n> __device__ __forceinline__ void cp_wait() { asm volatile("cp.async.wait_group %0;" ::"n"(n) : "memory"); }
__device__ __forceinline__ void fence_async_smem() { asm volatile("fence.proxy.async.shared::cta;" ::: "memory"); }
__device__ __forceinline__ void mbar_init(uint32_t a, uint32_t c) { asm volatile("mbarrier.init.shared.b64 [%0],%1;" ::"r"(a), "r"(c) : "memory"); }
__device__ __forceinline__ void mbar_spin(uint32_t a, uint32_t parity) {
    asm volatile(
        "{\n.reg .pred p;\n.reg .u32 c;\nmov.u32 c,0;\n"
        "LW:\nmbarrier.try_wait.parity.shared.b64 p,[%0],%1;\n@p bra LD;\n"
        "add.u32 c,c,1;\nsetp.lt.u32 p,c,%2;\n@p bra LW;\ntrap;\nLD:\n}\n" ::"r"(a), "r"(parity), "n"(SPIN_LIMIT) : "memory");
}
__device__ __forceinline__ void mbar_wait(uint32_t a, uint32_t parity) {
    uint32_t ok;
    asm volatile("{\n.reg .pred p;\nmbarrier.try_wait.parity.shared.b64 p,[%1],%2;\nselp.u32 %0,1,0,p;\n}\n" : "=r"(ok) : "r"(a), "r"(parity) : "memory");
    if (__builtin_expect(!ok, 0)) mbar_spin(a, parity);
}
__device__ __forceinline__ float tanh_f(float x) { float t; asm("tanh.approx.f32 %0,%1;" : "=f"(t) : "f"(x)); return t; }
__device__ __forceinline__ uint32_t pack_bf16(float lo, float hi) { uint32_t r; asm("cvt.rn.bf16x2.f32 %0,%1,%2;" : "=r"(r) : "f"(hi), "f"(lo)); return r; }
__device__ __forceinline__ uint32_t mul_bf16x2(uint32_t a, uint32_t b) { uint32_t r; asm("mul.rn.bf16x2 %0,%1,%2;" : "=r"(r) : "r"(a), "r"(b)); return r; }

#define WG_FENCE()  asm volatile("wgmma.fence.sync.aligned;" ::: "memory")
#define WG_COMMIT() asm volatile("wgmma.commit_group.sync.aligned;" ::: "memory")
#define WG_WAIT0()  asm volatile("wgmma.wait_group.sync.aligned 0;" ::: "memory")

template <int n> __device__ __forceinline__ void pin(float* d) {
#pragma unroll
    for (int i = 0; i < n; i++) asm volatile("" : "+f"(d[i])::"memory");
}
template <int n> __device__ __forceinline__ void pin(uint32_t* d) {
#pragma unroll
    for (int i = 0; i < n; i++) asm volatile("" : "+r"(d[i])::"memory");
}

template <int SC> __device__ __forceinline__ void mma64(float* d, const uint32_t* a, uint64_t desc) {
    asm volatile(
        "wgmma.mma_async.sync.aligned.m64n64k16.f32.bf16.bf16 "
        "{%0,%1,%2,%3,%4,%5,%6,%7,%8,%9,%10,%11,%12,%13,%14,%15,%16,%17,%18,%19,%20,%21,%22,%23,%24,%25,%26,%27,%28,%29,%30,%31},"
        "{%32,%33,%34,%35},%36,%37,1,1,0;"
        : "+f"(d[0]), "+f"(d[1]), "+f"(d[2]), "+f"(d[3]), "+f"(d[4]), "+f"(d[5]), "+f"(d[6]), "+f"(d[7]),
          "+f"(d[8]), "+f"(d[9]), "+f"(d[10]), "+f"(d[11]), "+f"(d[12]), "+f"(d[13]), "+f"(d[14]), "+f"(d[15]),
          "+f"(d[16]), "+f"(d[17]), "+f"(d[18]), "+f"(d[19]), "+f"(d[20]), "+f"(d[21]), "+f"(d[22]), "+f"(d[23]),
          "+f"(d[24]), "+f"(d[25]), "+f"(d[26]), "+f"(d[27]), "+f"(d[28]), "+f"(d[29]), "+f"(d[30]), "+f"(d[31])
        : "r"(a[0]), "r"(a[1]), "r"(a[2]), "r"(a[3]), "l"(desc), "n"(SC));
}
template <int SC> __device__ __forceinline__ void mma48(float* d, const uint32_t* a, uint64_t desc) {
    asm volatile(
        "wgmma.mma_async.sync.aligned.m64n48k16.f32.bf16.bf16 "
        "{%0,%1,%2,%3,%4,%5,%6,%7,%8,%9,%10,%11,%12,%13,%14,%15,%16,%17,%18,%19,%20,%21,%22,%23},"
        "{%24,%25,%26,%27},%28,%29,1,1,0;"
        : "+f"(d[0]), "+f"(d[1]), "+f"(d[2]), "+f"(d[3]), "+f"(d[4]), "+f"(d[5]), "+f"(d[6]), "+f"(d[7]),
          "+f"(d[8]), "+f"(d[9]), "+f"(d[10]), "+f"(d[11]), "+f"(d[12]), "+f"(d[13]), "+f"(d[14]), "+f"(d[15]),
          "+f"(d[16]), "+f"(d[17]), "+f"(d[18]), "+f"(d[19]), "+f"(d[20]), "+f"(d[21]), "+f"(d[22]), "+f"(d[23])
        : "r"(a[0]), "r"(a[1]), "r"(a[2]), "r"(a[3]), "l"(desc), "n"(SC));
}
__device__ __forceinline__ void mma8t(float* d, const uint32_t* a, uint64_t desc) {
    asm volatile(
        "wgmma.mma_async.sync.aligned.m64n8k16.f32.bf16.bf16 {%0,%1,%2,%3},{%4,%5,%6,%7},%8,1,1,1,1;"
        : "+f"(d[0]), "+f"(d[1]), "+f"(d[2]), "+f"(d[3])
        : "r"(a[0]), "r"(a[1]), "r"(a[2]), "r"(a[3]), "l"(desc));
}
__device__ __forceinline__ void set_acc(float& a0, float& a1, uint32_t u, uint32_t zero) {
    asm volatile("{\n.reg .pred p;\nsetp.ne.u32 p,%3,0;\n@!p prmt.b32 %0,%2,0,0x1044;\n@!p prmt.b32 %1,%2,0,0x3244;\n}\n"
                 : "+f"(a0), "+f"(a1) : "r"(u), "r"(zero));
}

__device__ __forceinline__ void scale_wfrag(uint32_t (*f)[4], uint32_t scale) {
#pragma unroll
    for (int k = 0; k < 4; k++)
#pragma unroll
        for (int j = 0; j < 4; j++) asm volatile("mul.rn.bf16x2 %0,%1,%2;" : "=r"(f[k][j]) : "r"(f[k][j]), "r"(scale));
}
__device__ __forceinline__ void load_wfrag(uint32_t (*f)[4], uint32_t a0, uint32_t a1) {
#pragma unroll
    for (int k = 0; k < 4; k++) {
#pragma unroll
        for (int h = 0; h < 2; h++) {
            const uint32_t l0 = lds32(a0 + k * 2048 + h * 1024), l1 = lds32(a1 + k * 2048 + h * 1024);
            f[k][2 * h]     = __byte_perm(l0, l1, 0x5410);
            f[k][2 * h + 1] = __byte_perm(l0, l1, 0x7632);
        }
    }
}
__device__ __forceinline__ uint32_t opaque(uint32_t v, uint32_t lane) { return __shfl_sync(0xffffffffu, v, lane); }

struct Params {
    const int* dst; const int* src; int plain; uint32_t* tab; const char* gw; const char* uw;
    const char* vw; const char* x; const char* e; char* out; char* rec;
};

template <int PHASE>
__global__ void __launch_bounds__(NT, 1) egc_kernel(const Params p) {
    extern __shared__ __align__(1024) char smem[];
    const uint32_t sb = (uint32_t)__cvta_generic_to_shared(smem);
    const uint32_t misc = sb + SM_MISC;
    const int tid = threadIdx.x, b = blockIdx.x;

    auto piece = [&](int k, bool init, bool go) {
        const uint32_t bar = misc + M_BAR + B_IN + k * 8;
        const uint32_t bytes = !(PHASE & 1) ? 0 : ((k & 3) == 3 && b == NB - 1 ? (NE - (NB - 1) * CH - 3 * PC) * 4 : PC * 4);
        if (init) {
            mbar_init(bar, 1);
            asm volatile("fence.mbarrier_init.release.cluster;" ::: "memory");
        }
        if (!go) return;
        asm volatile("mbarrier.arrive.expect_tx.shared.b64 _,[%0],%1;" ::"r"(bar), "r"(bytes) : "memory");
        if (PHASE & 1)
            asm volatile("cp.async.bulk.shared::cluster.global.mbarrier::complete_tx::bytes [%0],[%1],%2,[%3];" ::"r"(sb + SM_AU + k * 12288 + 6144),
                         "l"((k < 4 ? p.dst : p.src) + b * CH + (k & 3) * PC), "r"(bytes), "r"(bar) : "memory");
    };
    if (tid == 0) {
#pragma unroll
        for (int k = 0; k < 8; k++) piece(k, true, k < 4);
    }
    const int lane = tid & 31;
    const int warp = __shfl_sync(0xffffffffu, tid >> 5, 0);
    const int wg = warp >> 2, t7 = tid & 127;
    const int n0 = b * NPB;
    const int nlim = min(NPB, NN - n0);
    const int ew = b * CH + wg * PC;
    const int ecnt = (PHASE & 1) ? min(PC, NE - ew) : 0;
    if (tid == 64) {
#pragma unroll
        for (int k = 0; k < 8; k++) mbar_init(misc + M_BAR + B_X + k * 8, 128);
        mbar_init(misc + M_BAR + B_W, NT);
    }
    if (tid >= 32 && tid < 34 && b < 130) {
        const int r = 2 * b + tid - 32;
        asm volatile("prefetch.global.L2 [%0];" ::"l"(r < 132 ? p.gw + r * 128 : (r < 196 ? p.uw + (r - 132) * 128 : p.vw + (r - 196) * 128)) : "memory");
    }
    if (tid < M_ZEND / 4) sts32(misc + tid * 4, 0);
    if (tid == NT - 1) sts32(misc + M_BOFF + NB * 4, 0x40000000u);
    asm volatile("st.shared.v4.u32 [%0],{0,0,0,0};" ::"r"(sb + SM_CNT + tid * 16) : "memory");
    if (tid < 256) asm volatile("st.shared.v4.u32 [%0],{0,0,0,0};" ::"r"(sb + SM_CNT + 8192 + tid * 16) : "memory");
#pragma unroll
    for (int i = 0; i < 4; i++)
        if (i < 3 || tid < 256) asm volatile("st.shared.v4.u32 [%0],{%1,%1,%1,%1};" ::"r"(sb + SM_RING + tid * 16 + i * 8192), "r"(TRASH) : "memory");
    const uint32_t pa = sb + SM_AU + wg * 12288 + 6144 + t7 * 16;
#pragma unroll
    for (int i = 0; i < 3; i++)
        if ((t7 + 128 * i) * 4 >= ecnt) asm volatile("st.shared.v4.u32 [%0],{%1,%1,%1,%1};" ::"r"(pa + i * 2048), "r"(NB * NPB) : "memory");
    __syncthreads();
    const uint32_t padw = (n0 + t7) | ((XA - 4) << 16);
#pragma unroll
    for (int i = 2; i < 4; i++)
        if (i < 3 || tid < 256) asm volatile("st.shared.v4.u32 [%0],{%1,%1,%1,%1};" ::"r"(sb + SM_REC + tid * 16 + i * 8192), "r"(padw) : "memory");
    if (tid == 0) sts32(sb + SM_KEY + XA - 4, PAD_B | ((b * CH) << 12));
    uint64_t wsrc[4], xsrc[6];
    uint32_t wdst[4];
    const uint32_t wd = sb + (tid >> 3) * 128 + (((tid ^ (tid >> 3)) & 7) << 4);
#pragma unroll
    for (int k = 0; k < 4; k++) {
        const int j = (k + b) & 3;
        wdst[k] = wd + ((j & 1) ? SM_WE : SM_REC) + (j >> 1) * 8192;
        wsrc[k] = (uintptr_t)(j < 2 ? p.gw + j * 8192 : (j == 2 ? p.uw : p.vw)) + tid * 16;
        asm volatile("" : "+r"(wdst[k]), "+l"(wsrc[k]));
    }
#pragma unroll
    for (int i = 0; i < 3; i++) {
        const int n = t7 >> 3;
        const int r = n0 + 96 * wg + 16 * i + (n & 8) + 4 * (n & 1) + ((n >> 1) & 3);
#pragma unroll
        for (int bt = 0; bt < 2; bt++) {
            xsrc[bt * 3 + i] = (uintptr_t)p.x + (size_t)min(r + 48 * bt, NN - 1) * 128 + (t7 & 7) * 16;
            asm volatile("" : "+l"(xsrc[bt * 3 + i]));
        }
    }
    const uint32_t xd = sb + SM_AU + wg * 24576 + (t7 >> 3) * 128 + (((t7 ^ (t7 >> 3)) & 7) << 4);
    const int pp = warp + 12 * lane;
    const bool poller = lane < 11 && wg < 3;
    const uint32_t* fl = p.tab + pp * TABP + b;
    uint32_t fw = poller ? 0 : 0x80000000u;
    auto poll = [&]() { asm volatile("{.reg .pred p; setp.ge.s32 p,%0,0; @p ld.relaxed.gpu.global.u32 %0,[%1];}" : "+r"(fw) : "l"(fl) : "memory"); };
    uint32_t dd[12], ha[12], rk[12];
    if (t7 == 0) piece(4 + wg, false, true);
    mbar_wait(misc + M_BAR + B_IN + wg * 8, 0);
#pragma unroll
    for (int i = 0; i < 3; i++) {
        const uint4 d4 = lds128(pa + i * 2048);
        dd[4 * i] = d4.x; dd[4 * i + 1] = d4.y; dd[4 * i + 2] = d4.z; dd[4 * i + 3] = d4.w;
    }
#pragma unroll
    for (int j = 0; j < 12; j++) {
        ha[j] = __umulhi(dd[j], MAGIC) * 4;
        rk[j] = atoms_add(misc + M_HIST + ha[j], 4);
    }
#pragma unroll
    for (int k = 0; k < 4; k++) cp16(wdst[k], (const void*)wsrc[k]);
    if (tid < 32) cp16(wd + SM_WE + 16384, p.gw + tid * 16 + 16384);
    cp_arrive(misc + M_BAR + B_W);
    auto load_x = [&](int bt) {
#pragma unroll
        for (int k = 0; k < 3; k++) cp16(xd + bt * 12288 + k * 2048, (const void*)xsrc[bt * 3 + k]);
        cp_arrive(misc + M_BAR + B_X + wg * 16 + bt * 8);
    };
    load_x(0);
    __syncthreads();
    if (lane < 9 && warp * 9 + lane < NB) {
        const uint32_t a = misc + (warp * 9 + lane) * 4;
        sts32(a + M_BOFF, atoms_add(misc + M_VAR, (lds32(a + M_HIST) + 28) & ~31u));
    }
    __syncthreads();
#pragma unroll
    for (int j = 0; j < 12; j++) {
        rk[j] = min(rk[j] + lds32(misc + M_BOFF + ha[j]), XA - 4);
        const uint32_t t = ((uint32_t)(ew + t7 * 4 + (j >> 2) * 512 + (j & 3)) << 12) + dd[j] * 4 - ha[j] * NPB;
        dd[j] = t | ((t >> 3) & 2);
    }
#pragma unroll
    for (int j = 0; j < 12; j++) sts32(sb + SM_RING + rk[j], dd[j]);
    fence_async_smem();
    if (warp == 12) {
        asm volatile("bar.sync 14,512;" ::: "memory");
        if (lane == 0 && (PHASE & 1))
            asm volatile("cp.async.bulk.global.shared::cta.bulk_group [%0],[%1],%2;" ::"l"(p.rec + b * XAB), "r"(sb + SM_RING), "r"(lds32(misc + M_VAR)) : "memory");
        __syncwarp();
    } else asm volatile("bar.arrive 14,512;" ::: "memory");
    mbar_wait(misc + M_BAR + B_IN + 32 + wg * 8, 0);
#pragma unroll
    for (int i = 0; i < 3; i++) {
        const uint4 s4 = lds128(pa + 49152 + i * 2048);
        dd[4 * i] = s4.x; dd[4 * i + 1] = s4.y; dd[4 * i + 2] = s4.z; dd[4 * i + 3] = s4.w;
    }
#pragma unroll
    for (int j = 0; j < 12; j++)
        asm volatile("{.reg .b16 h; cvt.u16.u32 h,%1; st.shared.u16 [%0],h;}" ::"r"(sb + SM_RING + XA + (rk[j] >> 1)), "r"(dd[j]) : "memory");
    load_x(1);
    fence_async_smem();
    __syncthreads();
    if ((PHASE & 1) && warp == 12) {
        if (lane == 0) {
            const uint32_t bytes = lds32(misc + M_VAR);
            asm volatile("cp.async.bulk.global.shared::cta.bulk_group [%0],[%1],%2;" ::"l"(p.rec + b * XAB + XA), "r"(sb + SM_RING + XA), "r"((bytes / 2 + 31) & ~31u) : "memory");
            asm volatile("cp.async.bulk.commit_group;" ::: "memory");
        }
        uint32_t fv[5];
#pragma unroll
        for (int i = 0; i < 5; i++)
            fv[i] = 0x80000000u | ((lds32(misc + M_BOFF + (lane + 32 * i) * 4) >> 5) & 1023) | (((lds32(misc + M_HIST + (lane + 32 * i) * 4) + 28) >> 5) << 20);
        if (lane == 0) asm volatile("cp.async.bulk.wait_group 0;" ::: "memory");
        __syncwarp();
        asm volatile("fence.release.gpu;" ::: "memory");
#pragma unroll
        for (int i = 0; i < 5; i++)
            asm volatile("st.relaxed.gpu.global.u32 [%0],%1;" ::"l"(p.tab + b * TABP + lane + 32 * i), "r"(fv[i]) : "memory");
    }
    auto prefetch_e = [&](int q0, int q1) {
        const int n = min(CH, NE - b * CH) * 2;
        if (tid == 384) asm volatile("cp.async.bulk.prefetch.L2.global [%0],%1;" ::"l"(p.e + (size_t)b * CH * 8 + n * q0), "r"(n * (q1 - q0)) : "memory");
    };
    if (!(PHASE & 2)) { cp_commit(); cp_wait<0>(); return; }
    if (warp == 12) asm volatile("bar.arrive 5,416;" ::: "memory");

    const int g8 = lane >> 2, q = lane & 3, w4 = warp & 3;
    uint32_t wgt[4][4], wvl[4][4], af[4];
    uint32_t sd = 0;
    auto collect = [&](const int ab) {
        const int sub = lane >> (4 - ab), l = lane & (ab ? 7 : 15), mul = ab ? 16 : 32;
        const uint64_t gr = (uint64_t)(uintptr_t)p.rec + warp * XAB + ab * XA;
        const uint32_t db = sb + (ab ? SM_RING + XA : SM_KEY), thr = ((ab ? l : l >> 1) + 1) << 20;
#pragma unroll
        for (int k = 0; k < 11; k += 2 << ab) {
            const uint32_t sk = __shfl_sync(0xffffffffu, sd, k + sub);
            asm volatile("{.reg .pred p; setp.ge.u32 p,%2,%3; @p cp.async.cg.shared.global [%0],[%1],16;}"
                         ::"r"(db + l * 16 + ((sk >> 10) & 1023) * mul), "l"(gr + (sub * 12 * XAB + l * 16) + (sk & 1023) * mul + k * 12 * XAB), "r"(sk), "r"(thr) : "memory");
        }
        for (uint32_t m = __ballot_sync(0xffffffffu, sd >= (9u << 20)); m; m &= m - 1) {
            const int k = __ffs(m) - 1;
            const uint32_t sk = __shfl_sync(0xffffffffu, sd, k);
#pragma unroll 1
            for (uint32_t i = 8 * mul + lane * 16; i < (sk >> 20) * mul; i += 512)
                cp16(db + ((sk >> 10) & 1023) * mul + i, (const char*)gr + (sk & 1023) * mul + i + k * 12 * XAB);
        }
    };
    {
        const uint32_t wc = w4 * 32 + g8 * 4, wa = sb + q * 256 + (wc ^ (q * 32)), wb = (wa + 128) ^ 16;
        mbar_wait(misc + M_BAR + B_W, 0);
        load_wfrag(wgt, wa + SM_REC, wb + SM_REC);
        load_wfrag(wvl, wa + SM_REC + 8192, wb + SM_REC + 8192);
        if (wg < 3) asm volatile("bar.arrive 15,512;" ::: "memory");
        scale_wfrag(wgt, 0x3f003f00u);
        scale_wfrag(wvl, 0x3f003f00u);
#pragma unroll 1
        for (int bt = 0; bt < 2; bt++) {
            mbar_wait(misc + M_BAR + B_X + wg * 16 + bt * 8, 0);
            fence_async_smem();
            float da[24], du[24];
            uint32_t amax = 0;
            const uint32_t base = sb + SM_AU + wg * 24576 + bt * 12288;
            const uint32_t dx = ((base & 0x3ffff) >> 4) | (1 << 16);
            WG_FENCE();
            mma48<0>(da, wgt[0], mk64(dx, 0x40000040));
#pragma unroll
            for (int k = 1; k < 4; k++) mma48<1>(da, wgt[k], mk64(dx + 2 * k, 0x40000040));
            mma48<0>(du, wvl[0], mk64(dx, 0x40000040));
#pragma unroll
            for (int k = 1; k < 4; k++) mma48<1>(du, wvl[k], mk64(dx + 2 * k, 0x40000040));
            WG_COMMIT();
            if (bt) poll();
            WG_WAIT0();
            pin<24>(da); pin<24>(du);
            asm volatile("bar.sync %0,128;" ::"r"(1 + wg) : "memory");
            if (bt == 0) prefetch_e(0, 1);
#pragma unroll
            for (int j = 0; j < 12; j++) {
                const int i = (j >> 1) * 4 + (j & 1);
                const uint32_t a = pack_bf16(da[i], da[i + 2]);
                sts64(base + t7 * 8 + j * 1024, a, pack_bf16(du[i], du[i + 2]));
                asm("{.reg .b32 t; abs.bf16x2 t,%1; max.bf16x2 %0,%0,t;}" : "+r"(amax) : "r"(a));
            }
            if (max(amax & 0xffff, amax >> 16) >= 0x4280) sts32(misc + M_VAR + 8, 1);
        }
        if (wg < 3) {
            asm volatile("bar.sync 5,416;" ::: "memory");
#pragma unroll 1
            for (int it = 0; !__all_sync(0xffffffffu, fw >> 31); it++) {
                if (it == SPIN_LIMIT) __trap();
                poll();
            }
            asm volatile("fence.acquire.gpu;" ::: "memory");
            if (poller) {
                const uint32_t w = fw & 0x7fffffffu, c8 = w >> 20, pos = atoms_add(misc + M_VAR + 4, c8);
                sts32(misc + M_SEG + pp * 4, w);
                if (pos + c8 < CAP / 8) sd = w | (pos << 10);
            }
            __syncwarp();
            collect(0);
            cp_commit();
            load_wfrag(wgt, wa + SM_WE, wb + SM_WE);
            load_wfrag(wvl, wa + SM_WE + 8192, wb + SM_WE + 8192);
            const uint32_t ca = sb + SM_WE + 16384 + (q & 1) * 256 + (wc ^ ((q & 1) * 32));
            const uint32_t l0 = mul_bf16x2(lds32(ca), 0x3f003f00u), l1 = mul_bf16x2(lds32((ca + 128) ^ 16), 0x3f003f00u);
            af[2] = q < 2 ? 0 : __byte_perm(l0, l1, 0x5410);
            af[3] = q < 2 ? 0 : __byte_perm(l0, l1, 0x7632);
            collect(1);
            cp_commit();
            cp_wait<1>();
        } else {
            asm volatile("bar.sync 15,512;" ::: "memory");
#pragma unroll
            for (int i = 0; i < 8; i++)
                asm volatile("st.shared.v4.u32 [%0],{%1,%1,%1,%1};" ::"r"(sb + SM_REC + t7 * 16 + i * 2048), "r"(padw) : "memory");
            const int g4 = lane >> 3, c = lane & 7, r16 = lane >> 1, h = lane & 1;
            const uint32_t ring0 = sb + SM_RING + 2 * RINGW;
            wgt[0][0] = sb + SM_REC + w4 * 64 + g4 * 16;
            wgt[0][1] = sb + SM_REC + w4 * 64 + (r16 & 3) * 16 + (r16 >> 2) * 4 + 2;
            wgt[0][2] = ring0 + w4 * 2048 + g4 * 128 + ((c ^ g4) << 4);
            wgt[0][3] = w4 * 256 + r16 * 16;
            wgt[1][0] = w4 * 256 + r16 * 16 + h * 8;
            wgt[1][1] = ring0 + 16384 + w4 * 256 + r16 * 16 + h * 4;
            wgt[1][2] = (uint32_t)(uintptr_t)p.x + c * 16;
            wgt[1][3] = (uint32_t)(uintptr_t)p.e + h * 4;
            wgt[2][0] = 0x3f80;
            wgt[2][1] = (wgt[0][2] + 512) ^ 64;
        }
    }
    __syncthreads();
    const uint32_t total8 = lds32(misc + M_VAR + 4);
    const uint32_t n4 = total8 >= CAP / 8 ? 0 : total8 * 2;
    uint32_t kw[16], ca[16], rk2[16];
    uint2 sv[4];
    const bool last = warp * 32 + 3 * NT < n4;
    {
        auto fetch = [&](int k) {
            const uint4 v = lds128(sb + SM_KEY + tid * 16 + k * NT * 16);
            kw[4 * k] = v.x; kw[4 * k + 1] = v.y; kw[4 * k + 2] = v.z; kw[4 * k + 3] = v.w;
        };
        auto clip = [&](int k) {
            if (tid + NT * k >= n4) kw[4 * k] = kw[4 * k + 1] = kw[4 * k + 2] = kw[4 * k + 3] = TRASH;
        };
        auto count = [&](int k) {
            asm("lop3.b32 %0,%1,0x3f80,%2,0xea;" : "=r"(ca[k]) : "r"(kw[k] << 3), "r"(lane * 4));
            rk2[k] = atoms_add(sb + SM_CNT + ca[k], 4);
        };
#pragma unroll
        for (int k = 0; k < 3; k++) fetch(k);
        if (warp < 8) fetch(3);
        if (n4 < 3 * NT) { clip(0); clip(1); clip(2); }
#pragma unroll
        for (int k = 0; k < 12; k++) count(k);
        if (last) {
            clip(3);
#pragma unroll
            for (int k = 12; k < 16; k++) count(k);
        }
    }
    cp_wait<0>();
    __syncthreads();
    prefetch_e(1, 4);
    bool slow;
    uint32_t s1, s2, s3;
    uint32_t em[4];
    uint32_t g1 = 0, g2 = 0;
    {
        const uint32_t a0 = sb + SM_CNT + (tid >> 2) * 128 + (tid & 7) * 16, a1 = a0 ^ 64;
        uint4 c0, c1;
        uint32_t pre;
        if (wg < 3) {
            c0 = lds128(a0); c1 = lds128(a1);
            c0.y += c0.x; c0.z += c0.y; c0.w += c0.z;
            c1.x += c0.w; c1.y += c1.x; c1.z += c1.y; c1.w += c1.z;
            pre = atoms_add(misc + M_TOT + (tid >> 2) * 4, c1.w);
        }
        if (wg < 3) asm volatile("bar.sync %0,64;" ::"r"(8 + (warp >> 1)) : "memory");
        const uint32_t tb0 = sb + SM_RING;
        if (wg < 3) {
            uint32_t e = (tid & 63) * 4, cc[16];
            const uint32_t tw = tb0 + (warp >> 1) * 4096 + e;
#pragma unroll
            for (int i = 0; i < 4; i++) {
                const uint4 c = lds128(misc + M_TOT + (warp >> 1) * 64 + i * 16);
                cc[4 * i] = c.x; cc[4 * i + 1] = c.y; cc[4 * i + 2] = c.z; cc[4 * i + 3] = c.w;
            }
#pragma unroll
            for (int j = 0; j < 16; j++) {
                e = __viaddmax_u32(e | 252, 4, e + cc[j]);
                sts32(tw + j * 256, e);
            }
        }
        uint32_t v = 252 + lane * lds32(misc + M_VAR + 16);
#pragma unroll
        for (int k = 0; k < 4; k++) sv[k] = lds64(sb + SM_RING + XA + tid * 8 + k * NT * 8);
        __syncthreads();
        const uint32_t gmax = __reduce_max_sync(0xffffffffu, max(max(lds32(misc + M_TOT + lane * 4), lds32(misc + M_TOT + 128 + lane * 4)),
                                                                 lane < 31 ? lds32(misc + M_TOT + 256 + lane * 4) : 0));
        const uint32_t clast = lds32(misc + M_TOT + (NG - 2) * 4);
        uint32_t base = -256, es = -4;
#pragma unroll
        for (int i = 0; i < 5; i++) {
            v = lds32(tb0 + (16 * i + 15) * 256 + (v & 252));
            if (i + 1 == (warp >> 1)) es = base + v;
            base += v & ~255u;
        }
        const uint32_t totl = base + lds32(tb0 + (NG - 3) * 256 + (v & 252)) + 4 + clast;
        if (wg < 3) {
            const int g = tid >> 2;
            const uint32_t ra = tb0 + g * 256 + (es & 252);
            const uint32_t eb = (es & ~255u) + lds32(ra - 256), ee = ((es & ~255u) + lds32(ra)) >> 8;
            const uint32_t k = g == NG - 1 ? 0x40000000u : sb + SM_REC + ((g & 15) ? eb : es) + 4 + pre;
            asm volatile("st.shared.v4.u32 [%0],{%1,%2,%3,%4};" ::"r"(a0), "r"(k), "r"(k + c0.x), "r"(k + c0.y), "r"(k + c0.z) : "memory");
            asm volatile("st.shared.v4.u32 [%0],{%1,%2,%3,%4};" ::"r"(a1), "r"(k + c0.w), "r"(k + c1.x), "r"(k + c1.y), "r"(k + c1.z) : "memory");
            if (g < NG - 2) asm volatile("st.shared.u8 [%0],1;" ::"r"(misc + M_MASK + (ee & 31) * 4 + ((ee >> 5) & 3)) : "memory");
        }
        __syncthreads();
        const uint32_t lim = sb + SM_REC + CAP * 4 - 4;
        auto place = [&](int k) {
            const uint32_t v = (k & 2) ? sv[k >> 2].y : sv[k >> 2].x;
            sts32(rk2[k], __byte_perm(v, tid * 16 + (k >> 2) * NT * 16 + (k & 3) * 4, (k & 1) ? 0x5432 : 0x5410));
        };
        const uint32_t eb4 = lds32(misc + M_MASK + lane * 4);
        if (last) {
#pragma unroll
            for (int k = 12; k < 16; k++) ca[k] = lds32(sb + SM_CNT + ca[k]);
        }
#pragma unroll
        for (int k = 0; k < 12; k++) rk2[k] = min(rk2[k] + lds32(sb + SM_CNT + ca[k]), lim);
        s3 = (__reduce_max_sync(0xffffffffu, totl) + 255) >> 8;
        s1 = (s3 + 2) / 3;
        s2 = s1 + ((s3 - s1 + 1) >> 1);
        slow = p.plain || lds32(misc + M_VAR + 8) || total8 >= CAP / 8 || s3 >= CAP / 64 || gmax * 5 > (s3 - s2) * 256;
#pragma unroll
        for (int i = 0; i < 4; i++) {
            const uint32_t v = (eb4 >> (8 * i)) & 1;
            em[i] = __ballot_sync(0xffffffffu, v);
            if (i < 2 && i * 32 + lane < s1) g1 += v;
            if (i < 3 && i * 32 + lane < s2) g2 += v;
        }
        g1 = __reduce_add_sync(0xffffffffu, g1);
        g2 = __reduce_add_sync(0xffffffffu, g2);
#pragma unroll
        for (int k = 0; k < 12; k++) place(k);
        if (last) {
#pragma unroll
            for (int k = 12; k < 16; k++) rk2[k] = min(rk2[k] + ca[k], lim);
#pragma unroll
            for (int k = 12; k < 16; k++) place(k);
        }
    }
    auto reset_flags = [&]() {
        p.tab[(threadIdx.x - 384) * TABP + blockIdx.x] = 0;
        if (threadIdx.x < 384 + NB - 128) p.tab[(threadIdx.x - 256) * TABP + blockIdx.x] = 0;
    };
    if (slow) {
        if (wg == 3) reset_flags();
        float* agg = (float*)(smem + SM_AU);
        for (int i = tid; i < NPB * 64; i += NT) agg[i] = 0.f;
        __syncthreads();
        const __nv_bfloat162* X = (const __nv_bfloat162*)p.x;
        const __nv_bfloat162* G = (const __nv_bfloat162*)p.gw;
        const __nv_bfloat162* V = (const __nv_bfloat162*)p.vw;
        const __nv_bfloat162* U = (const __nv_bfloat162*)p.uw;
#pragma unroll 1
        for (int ps = 0; ps < NB; ps++) {
            const uint32_t w = lds32(misc + M_SEG + ps * 4);
            const int cnt = (w >> 20) * 8;
            const uint32_t* sa = (const uint32_t*)(p.rec + ps * XAB) + (w & 1023) * 8;
            const unsigned short* sn = (const unsigned short*)(p.rec + ps * XAB + XA) + (w & 1023) * 8;
#pragma unroll 1
            for (int i = warp; i < cnt; i += 16) {
                const uint2 r = make_uint2(__ldcg(sn + i), __ldcg(sa + i));
                if (r.y == TRASH) continue;
                const int dl = (r.y >> 2) & 511;
                const float2 xs = __bfloat1622float2(X[(size_t)r.x * 32 + lane]);
                const float2 xd = __bfloat1622float2(X[(size_t)(n0 + dl) * 32 + lane]);
                const __nv_bfloat16* ep = (const __nv_bfloat16*)p.e + (size_t)(r.y >> 12) * 4;
                float z0 = 0, z1 = 0, h0 = 0, h1 = 0;
#pragma unroll 1
                for (int k = 0; k < 64; k++) {
                    const float s = __shfl_sync(0xffffffffu, (k & 1) ? xs.y : xs.x, k >> 1);
                    const float d = __shfl_sync(0xffffffffu, (k & 1) ? xd.y : xd.x, k >> 1);
                    const float2 ga = __bfloat1622float2(G[k * 32 + lane]), gb = __bfloat1622float2(G[(64 + k) * 32 + lane]);
                    const float2 vv = __bfloat1622float2(V[k * 32 + lane]);
                    z0 += d * ga.x + s * gb.x; z1 += d * ga.y + s * gb.y;
                    h0 += s * vv.x; h1 += s * vv.y;
                }
#pragma unroll
                for (int k = 0; k < 4; k++) {
                    const float ev = __bfloat162float(ep[k]);
                    const float2 gc = __bfloat1622float2(G[(128 + k) * 32 + lane]);
                    z0 += ev * gc.x; z1 += ev * gc.y;
                }
                atomicAdd(agg + dl * 64 + 2 * lane, h0 / (1.f + __expf(-z0)));
                atomicAdd(agg + dl * 64 + 2 * lane + 1, h1 / (1.f + __expf(-z1)));
            }
        }
        __syncthreads();
#pragma unroll 1
        for (int dl = warp; dl < nlim; dl += 16) {
            const float2 xd = __bfloat1622float2(X[(size_t)(n0 + dl) * 32 + lane]);
            float u0 = agg[dl * 64 + 2 * lane], u1 = agg[dl * 64 + 2 * lane + 1];
#pragma unroll 1
            for (int k = 0; k < 64; k++) {
                const float d = __shfl_sync(0xffffffffu, (k & 1) ? xd.y : xd.x, k >> 1);
                const float2 uu = __bfloat1622float2(U[k * 32 + lane]);
                u0 += d * uu.x; u1 += d * uu.y;
            }
            ((uint32_t*)p.out)[(size_t)(n0 + dl) * 32 + lane] = pack_bf16(u0 / (1.f + __expf(-u0)), u1 / (1.f + __expf(-u1)));
        }
        return;
    }

    if (wg == 3) {
        asm volatile("setmaxnreg.dec.sync.aligned.u32 56;");
        uint32_t x0 = wgt[0][2], x1 = wgt[2][1], a4 = wgt[1][1], ra = wgt[0][0], rb = wgt[0][1];
        const uint32_t o1 = s1 * 256, o2 = s2 * 256, ar = wgt[0][3], a8 = wgt[1][0], xlo = wgt[1][2], elo = wgt[1][3], one = wgt[2][0];
        const uint32_t xhi = (uintptr_t)p.x >> 32, ehi = (uintptr_t)p.e >> 32;
        const uint32_t ar1 = ar | (g1 & 1) * 2, ar2 = ar | (g2 & 1) * 2;
        uint32_t ab = sb + SM_RING + 2 * RINGW + 16384, j = 0;
        auto key = [&](uint32_t a) {
            uint32_t o;
            asm volatile("ld.shared.u16 %0,[%1];" : "=r"(o) : "r"(a) : "memory");
            return lds32(sb + SM_KEY + o);
        };
        auto aux = [&](const int w, uint32_t m) {
            sts64(a8 + ab - w * RINGW, 0, 0);
            asm volatile("{.reg .b16 h; cvt.u16.u32 h,%1; st.shared.u16 [%0],h;}" ::"r"(((m & 0x80e) ^ (w == 0 ? ar : (w == 1 ? ar1 : ar2))) + ab - w * RINGW), "r"(one) : "memory");
        };
        auto fill = [&](const int w) {
            const uint32_t o = w == 0 ? 0 : (w == 1 ? o1 : o2);
            const uint4 r = lds128(ra + o);
            const uint32_t m = key(rb + o);
            const uint64_t xb = mk64(xlo, xhi);
            cp16row(x0 - w * RINGW, r.x & 0xffff, xb); cp16row(x1 - w * RINGW, r.y & 0xffff, xb);
            cp16row(x0 - w * RINGW + 1024, r.z & 0xffff, xb); cp16row(x1 - w * RINGW + 1024, r.w & 0xffff, xb);
            asm volatile("{.reg .u64 a; mad.wide.u32 a,%1,8,%2; cp.async.ca.shared.global [%0],[a],4;}" ::"r"(a4 - w * RINGW + 2056), "r"(m >> 12), "l"(mk64(elo, ehi)) : "memory");
            aux(w, m);
        };
        auto advance = [&]() {
            j++;
            const int dx = (j & 1) ? 8192 : -8192, da = (j & 1) ? 1024 : ((j & 2) ? 3072 : -5120);
            x0 += dx; x1 += dx; a4 += da; ab += da; ra += 256; rb += 256;
        };
        asm volatile("bar.sync 7,512;" ::: "memory");
        fill(0); cp_commit();
        fill(1); cp_commit();
        fill(2); cp_commit();
#pragma unroll
        for (int i = 0; i < 12; i++) sts32(a4 + 2048 + (i & 1) * 1024 + (i & 2) * 2048 - (i >> 2) * RINGW, 0);
        advance();
#pragma unroll 1
        for (int w = 0; w < 3; w++) {
            cp_wait<2>();
            fence_async_smem();
            asm volatile("bar.arrive %0,384;" ::"r"(8 + w) : "memory");
            fill(w);
            cp_commit();
        }
        advance();
        if (xhi == ((uintptr_t)p.x + (size_t)NN * 128) >> 32 && ehi == ((uintptr_t)p.e + (size_t)NE * 8) >> 32) {
            uint32_t hi[15];
            sts64(misc + M_BOFF + t7 * 8, xhi, ehi);
#pragma unroll
            for (int k = 0; k < 15; k++) asm volatile("ld.volatile.shared.u32 %0,[%1];" : "=r"(hi[k]) : "r"(misc + M_BOFF + t7 * 8 + (k % 5 == 4) * 4) : "memory");
#pragma unroll 1
            while (j < s3 - s2) {
#pragma unroll
                for (int w = 0; w < 3; w++) {
                    const uint32_t o = w == 0 ? 0 : (w == 1 ? o1 : o2), m = key(rb + o);
                    const uint4 r = lds128(ra + o);
                    if (w == 0) asm volatile("bar.sync 11,256;" ::: "memory");
                    if (w == 1) asm volatile("bar.sync 12,256;" ::: "memory");
                    if (w == 2) asm volatile("bar.sync 13,256;" ::: "memory");
                    cp_wait<2>();
                    fence_async_smem();
                    if (w == 0) asm volatile("bar.arrive 8,384;" ::: "memory");
                    if (w == 1) asm volatile("bar.arrive 9,384;" ::: "memory");
                    if (w == 2) asm volatile("bar.arrive 10,384;" ::: "memory");
                    aux(w, m);
                    cp16(x0 - w * RINGW, (const void*)mk64(__dp2a_lo(r.x, 128u, xlo), hi[5 * w]));
                    cp16(x1 - w * RINGW, (const void*)mk64(__dp2a_lo(r.y, 128u, xlo), hi[5 * w + 1]));
                    cp16(x0 - w * RINGW + 1024, (const void*)mk64(__dp2a_lo(r.z, 128u, xlo), hi[5 * w + 2]));
                    cp16(x1 - w * RINGW + 1024, (const void*)mk64(__dp2a_lo(r.w, 128u, xlo), hi[5 * w + 3]));
                    asm volatile("{.reg .u32 l; .reg .u64 a; mad.lo.u32 l,%1,8,%2; mov.b64 a,{l,%3}; cp.async.ca.shared.global [%0],[a],4;}"
                                 ::"r"(a4 - w * RINGW + 2056), "r"(m >> 12), "r"(elo), "r"(hi[5 * w + 4]) : "memory");
                    cp_commit();
                }
                advance();
            }
        }
        reset_flags();
#pragma unroll 1
        while (j < s1 + 2) {
#pragma unroll 1
            for (int w = 0; w < 3; w++) {
                asm volatile("bar.sync %0,256;" ::"r"(11 + w) : "memory");
                cp_wait<2>();
                fence_async_smem();
                if (j <= s1 || w == 0) asm volatile("bar.arrive %0,384;" ::"r"(8 + w) : "memory");
                if (j < (w == 0 ? s1 : (w == 1 ? s2 - s1 : s3 - s2))) fill(w);
                cp_commit();
            }
            advance();
        }
    } else {
        asm volatile("bar.arrive 7,512;" ::: "memory");
        asm volatile("setmaxnreg.inc.sync.aligned.u32 152;");
        scale_wfrag(wgt, 0x3f003f00u);
        scale_wfrag(wvl, 0x3e803e80u);
        const uint32_t zero = lds32(misc + M_VAR + 16);
        const uint32_t sa = wg == 0 ? 0 : (wg == 1 ? s1 : s2), S = (wg == 0 ? s1 : (wg == 1 ? s2 : s3)) - sa, smax = s1;
        const int gb = wg == 0 ? 0 : (wg == 1 ? g1 : g2);
        const uint32_t gl = (wg == 0 ? g1 : (wg == 1 ? g2 : NG - 2)) - gb;
        const uint32_t ring = sb + SM_RING + (2 - wg) * RINGW + zero;
        uint32_t mlo, mhi, fend;
        {
            const uint32_t m0 = sa < 32 ? em[0] : (sa < 64 ? em[1] : em[2]), m1 = sa < 32 ? em[1] : (sa < 64 ? em[2] : em[3]);
            const uint32_t m2 = sa < 32 ? em[2] : (sa < 64 ? em[3] : 0);
            uint64_t m = mk64(__funnelshift_r(m0, m1, sa), __funnelshift_r(m1, m2, sa));
            fend = (m >> (S - 1)) & 1;
            m = (m & ((1ull << S) - 1)) | (1ull << (S - 1));
            mlo = __reduce_or_sync(0xffffffffu, (uint32_t)m); mhi = __reduce_or_sync(0xffffffffu, (uint32_t)(m >> 32));
        }
        const uint32_t dkl = (((ring + 16384) & 0x3ffff) >> 4) | (128 << 16);
        const uint32_t ta = opaque(sb + SM_AU + gb * 1024 + t7 * 8, lane);
        const int lim0 = opaque((nlim - q - gb * 4) * 128, lane);
        const uint2 ob = make_uint2(opaque(8 + wg + lane * zero, lane), opaque((wg == 2 ? 8 : 9 + wg) + lane * zero, lane));
        const uint32_t eb = opaque(11 + wg + lane * zero, lane);
        const uint64_t outp = (uint64_t)(uintptr_t)p.out + (size_t)(n0 + gb * 4) * 128 + opaque(q * 128 + w4 * 32 + g8 * 4, lane);
        uint32_t dl = 0;
        uint32_t to = 3072 + zero;
        float dg[32], dv[32], acc[4];
        uint32_t pk[16];
        uint2 nx;
#pragma unroll
        for (int i = 0; i < 16; i++) pk[i] = 0;
        auto store_group = [&](float h0, float h1, uint32_t off) {
            const uint32_t o = pack_bf16(fmaf(h0, tanh_f(h0), h0), fmaf(h1, tanh_f(h1), h1));
            asm volatile("{\n.reg .pred p;\nsetp.lt.s32 p,%2,%3;\n@p st.global.u32 [%0],%1;\n}\n" ::"l"(outp + off), "r"(o), "r"(off), "r"(lim0) : "memory");
        };
        uint32_t dx = ((ring & 0x3ffff) >> 4) | (1 << 16), dk = dkl, dn = dkl - (120 << 16);
        int dxs = 512;
        uint32_t s = 0, f = 0;
        if (wg == 2) asm volatile("bar.arrive 8,384;" ::: "memory");
        {
#pragma unroll
            for (int i = 0; i < 4; i++) acc[i] = 0.f;
            const uint2 a0 = lds64(ta), b0 = lds64(ta + 1024);
            nx = lds64(ta + 2048);
            af[0] = __byte_perm(a0.x, b0.x, 0x5410);
            af[1] = __byte_perm(a0.x, b0.x, 0x7632);
            asm volatile("xor.b32 %0,%0,%1;" : "+r"(af[2]) : "r"(zero));
            asm volatile("xor.b32 %0,%0,%1;" : "+r"(af[3]) : "r"(zero));
            set_acc(acc[0], acc[2], wg ? 0 : a0.y, zero);
            set_acc(acc[1], acc[3], b0.y, zero);
        }
#define STEP(F, Q, tag)                                                                                                     \
    {                                                                                                                       \
        if (F) {                                                                                                            \
            af[0] = __byte_perm(af[0], nx.x, Q ? 0x5410 : 0x3254);                                                          \
            af[1] = __byte_perm(af[1], nx.x, Q ? 0x7610 : 0x3276);                                                          \
        }                                                                                                                   \
        asm volatile("bar.sync %0,384;" ::"r"(ob.x) : "memory");                                                            \
        pin<4>(acc); pin<16>(pk); pin<4>(af);                                                                               \
        WG_FENCE();                                                                                                         \
        mma64<0>(dg, af, mk64(dk, 8));                                                                                      \
        _Pragma("unroll") for (int k = 0; k < 4; k++) mma64<1>(dg, wgt[k], mk64(dx + 2 * k, 0x40000040));                   \
        WG_COMMIT();                                                                                                        \
        mma64<0>(dv, wvl[0], mk64(dx, 0x40000040));                                                                         \
        _Pragma("unroll") for (int k = 1; k < 4; k++) mma64<1>(dv, wvl[k], mk64(dx + 2 * k, 0x40000040));                   \
        WG_COMMIT();                                                                                                        \
        _Pragma("unroll") for (int k = 0; k < 4; k++) mma8t(acc, &pk[4 * k], mk64(dn + 16 * k, 8));       \
        WG_COMMIT();                                                                                                        \
        asm volatile("bar.arrive %0,384;" ::"r"(ob.y) : "memory");                                                          \
        f = mlo & 1;                                                                                                        \
        mlo = __funnelshift_r(mlo, mhi, 1); mhi >>= 1;                                                                      \
        s++;                                                                                                                \
        dn = dk - (120 << 16);                                                                                              \
        dk = dkl + (s & 1) * 64 + (s & 2) * 128;                                                                            \
        dx += dxs; dxs = -dxs;                                                                                              \
        asm volatile("wgmma.wait_group.sync.aligned 2;" ::: "memory");                                                      \
        pin<32>(dg);                                                                                                        \
        _Pragma("unroll") for (int i = 28; i < 32; i++) asm volatile("tanh.approx.f32 %0,%0; //" tag : "+f"(dg[i]));        \
                        \
        asm volatile("{.reg .pred p; setp.ne.u32 p,%0,0; @p st.shared.v4.f32 [%0],{%1,%2,%3,%4};}"                       \
                     ::"r"(zero), "f"(dg[28]), "f"(dg[29]), "f"(dg[30]), "f"(dg[31]) : "memory");                           \
        asm volatile("wgmma.wait_group.sync.aligned 1;" ::: "memory");                                                      \
        asm volatile("bar.arrive %0,256;" ::"r"(eb) : "memory");     \
        WG_WAIT0();                                                                                                         \
        pin<32>(dg); pin<32>(dv); pin<4>(acc); pin<16>(pk); pin<4>(af);                                                     \
        if (F) {                                                                                                            \
            store_group(acc[Q], acc[2 + Q], F == 2 && wg ? 0x7fffffff : dl + Q * 512);                                      \
                                  \
            if (F == 2) sts64(ta + 2048, __float_as_uint(acc[0]), __float_as_uint(acc[2]));                                 \
            set_acc(acc[Q], acc[2 + Q], nx.y, zero);                                                                        \
            nx = lds64(ta + to + Q * 1024);                                                                                 \
            if (Q) { to += 2048; dl += 1024; }                                                                              \
        }                                                                                                                   \
        _Pragma("unroll") for (int i = 0; i < 32; i += 2) {                                    \
            float t0 = dg[i], t1 = dg[i + 1];                                                                               \
            if (i < 28) {                                                                                                   \
                asm("tanh.approx.f32 %0,%1; //" tag : "=f"(t0) : "f"(dg[i]));                                               \
                asm("tanh.approx.f32 %0,%1; //" tag : "=f"(t1) : "f"(dg[i + 1]));                                           \
            }                                                                                                               \
            asm("fma.rn.f32 %0,%1,%0,%1; //" tag : "+f"(t0) : "f"(dv[i]));                                                  \
            asm("fma.rn.f32 %0,%1,%0,%1; //" tag : "+f"(t1) : "f"(dv[i + 1]));                                              \
            asm("cvt.rn.bf16x2.f32 %0,%1,%2; //" tag : "=r"(pk[i / 2]) : "f"(t1), "f"(t0));                                 \
        }                                                                                                                   \
        pin<16>(pk);                                                                                                        \
    }
#pragma unroll 1
        while (!f) STEP(0, 0, "e")
        STEP(2, 0, "f")
#pragma unroll 1
        while (true) {
#pragma unroll 1
            while (!f) STEP(0, 0, "a")
            if (!(mlo | mhi)) break;
            STEP(1, 1, "b")
#pragma unroll 1
            while (!f) STEP(0, 0, "c")
            if (!(mlo | mhi)) break;
            STEP(1, 0, "d")
        }
        if (S < smax) {
            asm volatile("bar.sync %0,384;" ::"r"(ob.x) : "memory");
            asm volatile("bar.arrive %0,384;" ::"r"(ob.y) : "memory");
            asm volatile("bar.arrive %0,256;" ::"r"(eb) : "memory");
        }
        if (wg == 0) asm volatile("bar.arrive 8,384;" ::: "memory");
        pin<4>(acc); pin<16>(pk);
        WG_FENCE();
#pragma unroll
        for (int k = 0; k < 4; k++) mma8t(acc, &pk[4 * k], mk64(dn + 16 * k, 8));
        WG_COMMIT();
        WG_WAIT0();
        pin<4>(acc); pin<16>(pk);
        {
            const bool odd = gl & 1;
            if (fend) store_group(odd ? acc[0] : acc[1], odd ? acc[2] : acc[3], gl * 512 - 512);
            uint2 ps = make_uint2(0, 0);
            if (wg < 2) ps = lds64(ta + gl * 1024 + 2048);
            store_group((odd ? acc[1] : acc[0]) + __uint_as_float(ps.x), (odd ? acc[3] : acc[2]) + __uint_as_float(ps.y), gl * 512);
        }
    }
}

}

extern "C" void kernel_launch(void* const* d_in, const int* in_sizes, int n_in, void* d_out, int out_size) {
    using namespace egc;
    static int fused = -1, plain = 0;
    static void *rec_ptr, *tab_ptr;
    if (fused < 0) {
        cudaGetSymbolAddress(&rec_ptr, g_rec);
        cudaGetSymbolAddress(&tab_ptr, g_tab);
        cudaFuncSetAttribute(egc_kernel<1>, cudaFuncAttributeMaxDynamicSharedMemorySize, SM_TOTAL);
        cudaFuncSetAttribute(egc_kernel<2>, cudaFuncAttributeMaxDynamicSharedMemorySize, SM_TOTAL);
        cudaFuncSetAttribute(egc_kernel<3>, cudaFuncAttributeMaxDynamicSharedMemorySize, SM_TOTAL);
        int dev = 0, sms = 0;
        cudaGetDevice(&dev);
        cudaDeviceGetAttribute(&sms, cudaDevAttrMultiProcessorCount, dev);
        fused = sms >= NB;
        cudaFuncAttributes fa;
        cudaFuncGetAttributes(&fa, fused ? egc_kernel<3> : egc_kernel<2>);
        plain = fa.numRegs != 128;
    }
    Params p;
    p.x = (const char*)d_in[0]; p.e = (const char*)d_in[1];
    p.src = (const int*)d_in[2]; p.dst = (const int*)d_in[3];
    p.uw = (const char*)d_in[4]; p.vw = (const char*)d_in[5]; p.gw = (const char*)d_in[6];
    p.out = (char*)d_out; p.rec = (char*)rec_ptr; p.tab = (uint32_t*)tab_ptr;
    if (in_sizes[0] != NN * 64 || in_sizes[2] != NE) return;
    p.plain = plain;
    if (fused) {
        egc_kernel<3><<<NB, NT, SM_TOTAL, cudaStreamPerThread>>>(p);
    } else {
        egc_kernel<1><<<NB, NT, SM_TOTAL, cudaStreamPerThread>>>(p);
        egc_kernel<2><<<NB, NT, SM_TOTAL, cudaStreamPerThread>>>(p);
    }
}
```
